```python
import torch

def _softmax(x, axis=-1):
    return torch.softmax(x, dim=axis)

def _gelu(x):
    return torch.nn.functional.gelu(x, approximate='tanh')

def _silu(x):
    return torch.nn.functional.silu(x)

def _sigmoid(x):
    return torch.sigmoid(x)

def _layernorm(x, axis=-1, eps=1e-05):
    m = x.mean(dim=axis, keepdim=True)
    v = x.var(dim=axis, keepdim=True, unbiased=False)
    return (x - m) / torch.sqrt(v + eps)

def _scatter_add(tgt, idx, src, axis=0):
    return tgt.clone().index_add_(axis, idx, src)

def _segment_sum(src, seg, n):
    out = torch.zeros((n,) + src.shape[1:], dtype=src.dtype)
    return out.index_add_(0, seg, src)

def _pad(x, pw):
    flat = tuple((v for pair in reversed(pw) for v in pair))
    return torch.nn.functional.pad(x, flat)
kernel_name = 'gated_mix__grouped_kv_mqa__mixer_gmlp__prompt'

def setup_inputs():

    _w = lambda a: (lambda t: t.to(torch.bfloat16) if t.is_floating_point() else t)(torch.as_tensor(a))

    def _A_setup():
        B, S, D, H = (1, 2048, 512, 32)
        Dh = D // H
        return {'x': _w((lambda *s: torch.randn(*s, dtype=torch.bfloat16) * 0.05)(B, S, D)), 'wq': _w((lambda *s: torch.randn(*s, dtype=torch.bfloat16) * 1.6)(D, H * Dh)), 'wk': _w((lambda *s: torch.randn(*s, dtype=torch.bfloat16) * 1.6)(D, Dh)), 'wv': _w((lambda *s: torch.randn(*s, dtype=torch.bfloat16) * 0.2)(D, Dh)), 'wo': _w((lambda *s: torch.randn(*s, dtype=torch.bfloat16) * 0.2)(H * Dh, D))}
    _A_in = _A_setup()

    def _B_setup():
        B, S, D, F = (1, 2048, 512, 1376)
        Fh = F // 2
        return {'x': _w((lambda *s: torch.randn(*s, dtype=torch.bfloat16) * 0.05)(B, S, D)), 'w_in': _w((lambda *s: torch.randn(*s, dtype=torch.bfloat16) * 0.8)(D, 2 * Fh)), 'w_sp': _w(0.01 * (lambda *s: torch.randn(*s, dtype=torch.bfloat16) * 0.8)(S, S)), 'b_sp': _w(1.0 + 0.01 * (lambda *s: torch.randn(*s, dtype=torch.bfloat16) * 0.05)(S)), 'w_out': _w((lambda *s: torch.randn(*s, dtype=torch.bfloat16) * 0.05)(Fh, D))}
    _B_in = _B_setup()
    return {'A_x': _A_in['x'], 'A_wq': _A_in['wq'], 'A_wk': _A_in['wk'], 'A_wv': _A_in['wv'], 'A_wo': _A_in['wo'], 'B_x': _B_in['x'], 'B_w_in': _B_in['w_in'], 'B_w_sp': _B_in['w_sp'], 'B_b_sp': _B_in['b_sp'], 'B_w_out': _B_in['w_out'], 'gate_w': _w((lambda *s: torch.randn(*s, dtype=torch.bfloat16) * 0.05)(512) * 16.0)}

def reference(A_x, A_wq, A_wk, A_wv, A_wo, B_x, B_w_in, B_w_sp, B_b_sp, B_w_out, gate_w):

    def _A_ref(x, wq, wk, wv, wo):
        B, S, D = x.shape
        H = 32
        Dh = D // H
        q = (lambda x, *d: x.permute(*d))((x @ wq).reshape(B, S, H, Dh), 0, 2, 1, 3)
        k = x @ wk
        v = x @ wv
        scores = torch.einsum('bhqd,bkd->bhqk', q, k) * Dh ** (-0.5)
        p = _softmax(scores, axis=-1)
        o = torch.einsum('bhqk,bkd->bhqd', p, v)
        return (lambda x, *d: x.permute(*d))(o, 0, 2, 1, 3).reshape(B, S, H * Dh) @ wo

    def _B_ref(x, w_in, w_sp, b_sp, w_out):
        B, S, D = x.shape
        F = w_in.shape[-1]
        Fh = F // 2
        z = _gelu(torch.einsum('bsd,df->bsf', x, w_in))
        z1 = z[..., :Fh].clone()
        z2 = _layernorm(z[..., Fh:], axis=-1)
        g = torch.einsum('ts,bsf->btf', w_sp, z2) + b_sp[None, :, None]
        return torch.einsum('bsf,fd->bsd', z1 * g, w_out)
    x = A_x
    g = _sigmoid((x * gate_w).sum(-1, keepdims=True))
    a = _A_ref(x, A_wq, A_wk, A_wv, A_wo)
    b = _B_ref(x, B_w_in, B_w_sp, B_b_sp, B_w_out)
    return g * a + (1 - g) * b
```

```cpp
#include <cuda_runtime.h>
#include <cuda_bf16.h>
#include <cuda.h>
#include <stdint.h>

namespace {

constexpr int NCTA = 128;
#define PAT 0xFF80
#define W2 1
#define GB 1
#define HINT ", 4000"
#define NSLEEP "nanosleep.u32 200;\n"
#define QPRI 1
#define GD 1

constexpr uint32_t SM_X    = 0;
constexpr uint32_t SM_RING = 65536;
constexpr uint32_t STAGE   = 32768;
constexpr uint32_t SM_KV   = SM_RING + 4 * STAGE;
constexpr uint32_t KVSLOT  = 5120;
constexpr uint32_t SM_Q    = SM_KV + 20480;
constexpr uint32_t SM_GW   = SM_KV + 32768;
constexpr uint32_t SM_GATE = SM_GW + 1280;
constexpr uint32_t SM_BAR  = SM_GATE + 256;
constexpr uint32_t SM_EPOCH = SM_BAR + 512;
constexpr uint32_t SM_TOTAL = SM_EPOCH + 256;
constexpr int B_H = 0, B_X = 8, B_FULL = 12, B_EMPTY = 16, B_KVF = 20, B_KVE = 24, B_XDEAD = 32, B_KN = 34, B_PUB = 35, B_Q0 = 36, B_KVM = 37, B_KVD = 28, B_OL = 29, B_KV0 = 31;

__device__ uint32_t g_launch_ctr;
__device__ __align__(128) uint32_t g_kv_flag[32];
__device__ __align__(128) uint32_t g_st_flag[32];
__device__ __align__(128) uint32_t g_z_flag[4][32];
__device__ __align__(128) uint32_t g_u_flag[32];
__device__ __align__(128) float    g_kmax[32][4];
__device__ __align__(128) float2   g_stats[32][4][64];
__device__ __align__(1024) uint32_t g_kv[32][1024];
__device__ __align__(1024) uint32_t g_z2n[4][32][5632];
__device__ __align__(1024) uint4    g_kvm[2][32][2][128];
__device__ __align__(1024) uint32_t g_u[32][88 * 256];
__device__ __align__(1024) uint4    g_o[32][4][4][256];
#define PROF_T(i)
#define PROF_P(i)
#define PROF_END()

struct Maps { CUtensorMap x, wq, win, wsp, wout, wo; };

__device__ __forceinline__ void mbar_init(uint32_t a, uint32_t c) { asm volatile("mbarrier.init.shared::cta.b64 [%0], %1;" :: "r"(a), "r"(c) : "memory"); }
__device__ __forceinline__ void mbar_expect(uint32_t a, uint32_t b) { asm volatile("mbarrier.arrive.expect_tx.shared::cta.b64 _, [%0], %1;" :: "r"(a), "r"(b) : "memory"); }
__device__ __forceinline__ void mbar_arrive(uint32_t a) { asm volatile("mbarrier.arrive.shared::cta.b64 _, [%0];" :: "r"(a) : "memory"); }
__device__ __forceinline__ void mbar_wait(uint32_t a, uint32_t ph) {
    asm volatile("{\n.reg .pred p;\n.reg .u32 n;\nmov.u32 n, 0;\n"
                 "W%=:\nmbarrier.try_wait.parity.shared::cta.b64 p, [%0], %1" HINT ";\n@p bra D%=;\n"
                 "add.u32 n, n, 1;\nsetp.lt.u32 p, n, 0x100000;\n@p bra W%=;\ntrap;\nD%=:\n}" :: "r"(a), "r"(ph) : "memory");
}
__device__ __forceinline__ uint32_t mbar_test(uint32_t a, uint32_t ph) {
    uint32_t ok;
    asm volatile("{.reg .pred p; mbarrier.test_wait.parity.shared::cta.b64 p, [%1], %2; selp.u32 %0, 1, 0, p;}" : "=r"(ok) : "r"(a), "r"(ph) : "memory");
    return ok;
}
__device__ __forceinline__ void tma2d(uint32_t dst, const CUtensorMap* m, int c0, int c1, uint32_t bar) {
    asm volatile("cp.async.bulk.tensor.2d.shared::cluster.global.mbarrier::complete_tx::bytes [%0], [%1, {%3, %4}], [%2];"
                 :: "r"(dst), "l"(m), "r"(bar), "r"(c0), "r"(c1) : "memory");
}
__device__ __forceinline__ uint4 ldg_stream(const uint4* p) {
    uint4 v; asm volatile("ld.global.nc.L1::no_allocate.v4.u32 {%0,%1,%2,%3}, [%4];" : "=r"(v.x), "=r"(v.y), "=r"(v.z), "=r"(v.w) : "l"(p)); return v;
}
__device__ __forceinline__ void tma3d(uint32_t dst, const CUtensorMap* m, int c0, int c1, int c2, uint32_t bar) {
    asm volatile("cp.async.bulk.tensor.3d.shared::cluster.global.mbarrier::complete_tx::bytes [%0], [%1, {%3, %4, %5}], [%2];"
                 :: "r"(dst), "l"(m), "r"(bar), "r"(c0), "r"(c1), "r"(c2) : "memory");
}
__device__ __forceinline__ void bulk_ld(uint32_t dst, const void* src, uint32_t bytes, uint32_t bar) {
    asm volatile("cp.async.bulk.shared::cluster.global.mbarrier::complete_tx::bytes [%0], [%1], %2, [%3];"
                 :: "r"(dst), "l"(src), "r"(bytes), "r"(bar) : "memory");
}
__device__ __forceinline__ void l2_prefetch(const void* src, uint32_t bytes) {
    asm volatile("cp.async.bulk.prefetch.L2.global [%0], %1;" :: "l"(src), "r"(bytes) : "memory");
}
__device__ __forceinline__ void red_rel(uint32_t* p) { asm volatile("red.release.gpu.global.add.u32 [%0], 1;" :: "l"(p) : "memory"); }
__device__ __forceinline__ void fence_async_global() { asm volatile("fence.proxy.async.global;" ::: "memory"); }
__device__ __forceinline__ void fence_async_smem() { asm volatile("fence.proxy.async.shared::cta;" ::: "memory"); }
__device__ __forceinline__ void bar_sync(int id) { asm volatile("bar.sync %0, 128;" :: "r"(id) : "memory"); }
__device__ __forceinline__ uint32_t ld_acq(const uint32_t* p) { uint32_t v; asm volatile("ld.acquire.gpu.global.u32 %0, [%1];" : "=r"(v) : "l"(p) : "memory"); return v; }
__device__ __forceinline__ uint4 ld_relaxed4(const uint4* p) {
    uint4 v; asm volatile("ld.relaxed.gpu.global.v4.u32 {%0,%1,%2,%3}, [%4];" : "=r"(v.x), "=r"(v.y), "=r"(v.z), "=r"(v.w) : "l"(p) : "memory"); return v;
}
__device__ __forceinline__ void st_mail(uint4* p, uint32_t a, uint32_t b, uint32_t c, uint32_t d);
__device__ __forceinline__ uint32_t min4(uint4 v) { return min(min(v.x, v.y), min(v.z, v.w)); }
__device__ __forceinline__ void st_relaxed4(uint4* p, uint32_t a, uint32_t b, uint32_t c, uint32_t d) {
    asm volatile("st.relaxed.gpu.global.v4.u32 [%0], {%1,%2,%3,%4};" :: "l"(p), "r"(a), "r"(b), "r"(c), "r"(d) : "memory");
}
__device__ __forceinline__ void st_mail(uint4* p, uint32_t a, uint32_t b, uint32_t c, uint32_t d) { st_relaxed4(p, max(a, 1u), max(b, 1u), max(c, 1u), max(d, 1u)); }
__device__ __forceinline__ void poll_all(const uint32_t* p, uint32_t target) {
    for (int n = 0; !__all_sync(~0u, (int)(ld_acq(p) - target) >= 0) && n < 0x400000; n++) __nanosleep(100);
}
__device__ __forceinline__ void warp_arrive(uint32_t a, int lane) { __syncwarp(); if (lane == 0) mbar_arrive(a); }
__device__ __forceinline__ void wfence() { asm volatile("wgmma.fence.sync.aligned;" ::: "memory"); }
__device__ __forceinline__ void wcommit() { asm volatile("wgmma.commit_group.sync.aligned;" ::: "memory"); }
template<int N> __device__ __forceinline__ void wwait() { asm volatile("wgmma.wait_group.sync.aligned %0;" :: "n"(N) : "memory"); }
template<int N> __device__ __forceinline__ void pin(float (&a)[N]) {
#pragma unroll
    for (int i = 0; i < N; i++) asm volatile("" : "+f"(a[i]) :: "memory");
}
template<int N> __device__ __forceinline__ void pinu(uint32_t (&a)[N]) {
#pragma unroll
    for (int i = 0; i < N; i++) asm volatile("" : "+r"(a[i]) :: "memory");
}
template<int N> __device__ __forceinline__ void zero(float (&a)[N]) {
#pragma unroll
    for (int i = 0; i < N; i++) { a[i] = 0.f; asm volatile("" : "+f"(a[i]) :: "memory"); }
}
__device__ __forceinline__ uint64_t mkdesc(uint32_t addr, uint32_t lbo, uint32_t sbo, uint32_t swz) {
    uint32_t lo = ((addr & 0x3FFFF) >> 4) | ((lbo >> 4) << 16), hi = (sbo >> 4) | (swz << 30);
    return ((uint64_t)hi << 32) | lo;
}
__device__ __forceinline__ float ex2(float x) { float y; asm("ex2.approx.ftz.f32 %0, %1;" : "=f"(y) : "f"(x)); return y; }
__device__ __forceinline__ uint32_t pack(float lo, float hi) { uint32_t r; asm("cvt.rn.bf16x2.f32 %0, %1, %2;" : "=r"(r) : "f"(hi), "f"(lo)); return r; }
__device__ __forceinline__ float bf_lo(uint32_t v) { return __uint_as_float(v << 16); }
__device__ __forceinline__ float bf_hi(uint32_t v) { return __uint_as_float(v & 0xFFFF0000u); }
__device__ __forceinline__ float gelu2(float x) {
    float u = x * fmaf(x * x, 0.7978845608f * 0.044715f, 0.7978845608f), t;
    asm("tanh.approx.f32 %0, %1;" : "=f"(t) : "f"(u));
    return fmaf(x, t, x);
}
__device__ __forceinline__ uint32_t bf2_fma(uint32_t a, uint32_t b, uint32_t c) { uint32_t d; asm("fma.rn.bf16x2 %0, %1, %2, %3;" : "=r"(d) : "r"(a), "r"(b), "r"(c)); return d; }
__device__ __forceinline__ uint32_t bf2_mul(uint32_t a, uint32_t b) { uint32_t d; asm("mul.rn.bf16x2 %0, %1, %2;" : "=r"(d) : "r"(a), "r"(b)); return d; }
__device__ __forceinline__ bool elect() { uint32_t p; asm volatile("{.reg .pred p; elect.sync _|p, 0xffffffff; selp.u32 %0, 1, 0, p;}" : "=r"(p)); return p; }
__device__ __forceinline__ float quad_sum(float v) { v += __shfl_xor_sync(~0u, v, 1); return v + __shfl_xor_sync(~0u, v, 2); }
__device__ __forceinline__ float quad_max(float v) { v = fmaxf(v, __shfl_xor_sync(~0u, v, 1)); return fmaxf(v, __shfl_xor_sync(~0u, v, 2)); }

__device__ __forceinline__ void wg_qk64s(float (&d)[32], uint64_t da, uint64_t db) {
    asm volatile("wgmma.mma_async.sync.aligned.m64n64k16.f32.bf16.bf16 {%0,%1,%2,%3,%4,%5,%6,%7,%8,%9,%10,%11,%12,%13,%14,%15,%16,%17,%18,%19,%20,%21,%22,%23,%24,%25,%26,%27,%28,%29,%30,%31}, %32, %33, 0, 1, 1, 0, 0;"
        : "+f"(d[0]), "+f"(d[1]), "+f"(d[2]), "+f"(d[3]), "+f"(d[4]), "+f"(d[5]), "+f"(d[6]), "+f"(d[7]), "+f"(d[8]), "+f"(d[9]), "+f"(d[10]), "+f"(d[11]), "+f"(d[12]), "+f"(d[13]), "+f"(d[14]), "+f"(d[15]), "+f"(d[16]), "+f"(d[17]), "+f"(d[18]), "+f"(d[19]), "+f"(d[20]), "+f"(d[21]), "+f"(d[22]), "+f"(d[23]), "+f"(d[24]), "+f"(d[25]), "+f"(d[26]), "+f"(d[27]), "+f"(d[28]), "+f"(d[29]), "+f"(d[30]), "+f"(d[31])
        : "l"(da), "l"(db));
}
__device__ __forceinline__ void wg_rs128(float (&d)[64], uint32_t a0, uint32_t a1, uint32_t a2, uint32_t a3, uint64_t db) {
    asm volatile("wgmma.mma_async.sync.aligned.m64n128k16.f32.bf16.bf16 {%0,%1,%2,%3,%4,%5,%6,%7,%8,%9,%10,%11,%12,%13,%14,%15,%16,%17,%18,%19,%20,%21,%22,%23,%24,%25,%26,%27,%28,%29,%30,%31,%32,%33,%34,%35,%36,%37,%38,%39,%40,%41,%42,%43,%44,%45,%46,%47,%48,%49,%50,%51,%52,%53,%54,%55,%56,%57,%58,%59,%60,%61,%62,%63}, {%64,%65,%66,%67}, %68, 1, 1, 1, 1;"
        : "+f"(d[0]), "+f"(d[1]), "+f"(d[2]), "+f"(d[3]), "+f"(d[4]), "+f"(d[5]), "+f"(d[6]), "+f"(d[7]), "+f"(d[8]), "+f"(d[9]), "+f"(d[10]), "+f"(d[11]), "+f"(d[12]), "+f"(d[13]), "+f"(d[14]), "+f"(d[15]), "+f"(d[16]), "+f"(d[17]), "+f"(d[18]), "+f"(d[19]), "+f"(d[20]), "+f"(d[21]), "+f"(d[22]), "+f"(d[23]), "+f"(d[24]), "+f"(d[25]), "+f"(d[26]), "+f"(d[27]), "+f"(d[28]), "+f"(d[29]), "+f"(d[30]), "+f"(d[31]), "+f"(d[32]), "+f"(d[33]), "+f"(d[34]), "+f"(d[35]), "+f"(d[36]), "+f"(d[37]), "+f"(d[38]), "+f"(d[39]), "+f"(d[40]), "+f"(d[41]), "+f"(d[42]), "+f"(d[43]), "+f"(d[44]), "+f"(d[45]), "+f"(d[46]), "+f"(d[47]), "+f"(d[48]), "+f"(d[49]), "+f"(d[50]), "+f"(d[51]), "+f"(d[52]), "+f"(d[53]), "+f"(d[54]), "+f"(d[55]), "+f"(d[56]), "+f"(d[57]), "+f"(d[58]), "+f"(d[59]), "+f"(d[60]), "+f"(d[61]), "+f"(d[62]), "+f"(d[63])
        : "r"(a0), "r"(a1), "r"(a2), "r"(a3), "l"(db));
}
__device__ __forceinline__ void wg_pv24(float (&d)[12], uint32_t a0, uint32_t a1, uint32_t a2, uint32_t a3, uint64_t db) {
    asm volatile("wgmma.mma_async.sync.aligned.m64n24k16.f32.bf16.bf16 {%0,%1,%2,%3,%4,%5,%6,%7,%8,%9,%10,%11}, {%12,%13,%14,%15}, %16, 1, 1, 1, 1;"
        : "+f"(d[0]), "+f"(d[1]), "+f"(d[2]), "+f"(d[3]), "+f"(d[4]), "+f"(d[5]), "+f"(d[6]), "+f"(d[7]), "+f"(d[8]), "+f"(d[9]), "+f"(d[10]), "+f"(d[11])
        : "r"(a0), "r"(a1), "r"(a2), "r"(a3), "l"(db));
}
__device__ __forceinline__ void wg_ss32(float (&d)[16], uint64_t da, uint64_t db, bool acc) {
    asm volatile("{.reg .pred p; setp.ne.b32 p, %18, 0; wgmma.mma_async.sync.aligned.m64n32k16.f32.bf16.bf16 {%0,%1,%2,%3,%4,%5,%6,%7,%8,%9,%10,%11,%12,%13,%14,%15}, %16, %17, p, 1, 1, 0, 1;}"
        : "+f"(d[0]), "+f"(d[1]), "+f"(d[2]), "+f"(d[3]), "+f"(d[4]), "+f"(d[5]), "+f"(d[6]), "+f"(d[7]), "+f"(d[8]), "+f"(d[9]), "+f"(d[10]), "+f"(d[11]), "+f"(d[12]), "+f"(d[13]), "+f"(d[14]), "+f"(d[15])
        : "l"(da), "l"(db), "r"((int)acc));
}
__device__ __forceinline__ void wg_ss8k(float (&d)[4], uint64_t da, uint64_t db, bool acc) {
    asm volatile("{.reg .pred p; setp.ne.b32 p, %6, 0; wgmma.mma_async.sync.aligned.m64n8k16.f32.bf16.bf16 {%0,%1,%2,%3}, %4, %5, p, 1, 1, 0, 0;}"
        : "+f"(d[0]), "+f"(d[1]), "+f"(d[2]), "+f"(d[3])
        : "l"(da), "l"(db), "r"((int)acc));
}
__device__ __forceinline__ void wg_ss64(float (&d)[32], uint64_t da, uint64_t db, bool acc) {
    asm volatile("{.reg .pred p; setp.ne.b32 p, %34, 0; wgmma.mma_async.sync.aligned.m64n64k16.f32.bf16.bf16 {%0,%1,%2,%3,%4,%5,%6,%7,%8,%9,%10,%11,%12,%13,%14,%15,%16,%17,%18,%19,%20,%21,%22,%23,%24,%25,%26,%27,%28,%29,%30,%31}, %32, %33, p, 1, 1, 0, 1;}"
        : "+f"(d[0]), "+f"(d[1]), "+f"(d[2]), "+f"(d[3]), "+f"(d[4]), "+f"(d[5]), "+f"(d[6]), "+f"(d[7]), "+f"(d[8]), "+f"(d[9]), "+f"(d[10]), "+f"(d[11]), "+f"(d[12]), "+f"(d[13]), "+f"(d[14]), "+f"(d[15]), "+f"(d[16]), "+f"(d[17]), "+f"(d[18]), "+f"(d[19]), "+f"(d[20]), "+f"(d[21]), "+f"(d[22]), "+f"(d[23]), "+f"(d[24]), "+f"(d[25]), "+f"(d[26]), "+f"(d[27]), "+f"(d[28]), "+f"(d[29]), "+f"(d[30]), "+f"(d[31])
        : "l"(da), "l"(db), "r"((int)acc));
}
__device__ __forceinline__ void wg_ss128(float (&d)[64], uint64_t da, uint64_t db, bool acc) {
    asm volatile("{.reg .pred p; setp.ne.b32 p, %66, 0; wgmma.mma_async.sync.aligned.m64n128k16.f32.bf16.bf16 {%0,%1,%2,%3,%4,%5,%6,%7,%8,%9,%10,%11,%12,%13,%14,%15,%16,%17,%18,%19,%20,%21,%22,%23,%24,%25,%26,%27,%28,%29,%30,%31,%32,%33,%34,%35,%36,%37,%38,%39,%40,%41,%42,%43,%44,%45,%46,%47,%48,%49,%50,%51,%52,%53,%54,%55,%56,%57,%58,%59,%60,%61,%62,%63}, %64, %65, p, 1, 1, 0, 1;}"
        : "+f"(d[0]), "+f"(d[1]), "+f"(d[2]), "+f"(d[3]), "+f"(d[4]), "+f"(d[5]), "+f"(d[6]), "+f"(d[7]), "+f"(d[8]), "+f"(d[9]), "+f"(d[10]), "+f"(d[11]), "+f"(d[12]), "+f"(d[13]), "+f"(d[14]), "+f"(d[15]), "+f"(d[16]), "+f"(d[17]), "+f"(d[18]), "+f"(d[19]), "+f"(d[20]), "+f"(d[21]), "+f"(d[22]), "+f"(d[23]), "+f"(d[24]), "+f"(d[25]), "+f"(d[26]), "+f"(d[27]), "+f"(d[28]), "+f"(d[29]), "+f"(d[30]), "+f"(d[31]), "+f"(d[32]), "+f"(d[33]), "+f"(d[34]), "+f"(d[35]), "+f"(d[36]), "+f"(d[37]), "+f"(d[38]), "+f"(d[39]), "+f"(d[40]), "+f"(d[41]), "+f"(d[42]), "+f"(d[43]), "+f"(d[44]), "+f"(d[45]), "+f"(d[46]), "+f"(d[47]), "+f"(d[48]), "+f"(d[49]), "+f"(d[50]), "+f"(d[51]), "+f"(d[52]), "+f"(d[53]), "+f"(d[54]), "+f"(d[55]), "+f"(d[56]), "+f"(d[57]), "+f"(d[58]), "+f"(d[59]), "+f"(d[60]), "+f"(d[61]), "+f"(d[62]), "+f"(d[63])
        : "l"(da), "l"(db), "r"((int)acc));
}
__device__ __forceinline__ void wg_ss176(float (&d)[88], uint64_t da, uint64_t db, bool acc) {
    asm volatile("{.reg .pred p; setp.ne.b32 p, %90, 0; wgmma.mma_async.sync.aligned.m64n176k16.f32.bf16.bf16 {%0,%1,%2,%3,%4,%5,%6,%7,%8,%9,%10,%11,%12,%13,%14,%15,%16,%17,%18,%19,%20,%21,%22,%23,%24,%25,%26,%27,%28,%29,%30,%31,%32,%33,%34,%35,%36,%37,%38,%39,%40,%41,%42,%43,%44,%45,%46,%47,%48,%49,%50,%51,%52,%53,%54,%55,%56,%57,%58,%59,%60,%61,%62,%63,%64,%65,%66,%67,%68,%69,%70,%71,%72,%73,%74,%75,%76,%77,%78,%79,%80,%81,%82,%83,%84,%85,%86,%87}, %88, %89, p, 1, 1, 0, 1;}"
        : "+f"(d[0]), "+f"(d[1]), "+f"(d[2]), "+f"(d[3]), "+f"(d[4]), "+f"(d[5]), "+f"(d[6]), "+f"(d[7]), "+f"(d[8]), "+f"(d[9]), "+f"(d[10]), "+f"(d[11]), "+f"(d[12]), "+f"(d[13]), "+f"(d[14]), "+f"(d[15]), "+f"(d[16]), "+f"(d[17]), "+f"(d[18]), "+f"(d[19]), "+f"(d[20]), "+f"(d[21]), "+f"(d[22]), "+f"(d[23]), "+f"(d[24]), "+f"(d[25]), "+f"(d[26]), "+f"(d[27]), "+f"(d[28]), "+f"(d[29]), "+f"(d[30]), "+f"(d[31]), "+f"(d[32]), "+f"(d[33]), "+f"(d[34]), "+f"(d[35]), "+f"(d[36]), "+f"(d[37]), "+f"(d[38]), "+f"(d[39]), "+f"(d[40]), "+f"(d[41]), "+f"(d[42]), "+f"(d[43]), "+f"(d[44]), "+f"(d[45]), "+f"(d[46]), "+f"(d[47]), "+f"(d[48]), "+f"(d[49]), "+f"(d[50]), "+f"(d[51]), "+f"(d[52]), "+f"(d[53]), "+f"(d[54]), "+f"(d[55]), "+f"(d[56]), "+f"(d[57]), "+f"(d[58]), "+f"(d[59]), "+f"(d[60]), "+f"(d[61]), "+f"(d[62]), "+f"(d[63]), "+f"(d[64]), "+f"(d[65]), "+f"(d[66]), "+f"(d[67]), "+f"(d[68]), "+f"(d[69]), "+f"(d[70]), "+f"(d[71]), "+f"(d[72]), "+f"(d[73]), "+f"(d[74]), "+f"(d[75]), "+f"(d[76]), "+f"(d[77]), "+f"(d[78]), "+f"(d[79]), "+f"(d[80]), "+f"(d[81]), "+f"(d[82]), "+f"(d[83]), "+f"(d[84]), "+f"(d[85]), "+f"(d[86]), "+f"(d[87])
        : "l"(da), "l"(db), "r"((int)acc));
}

__device__ __forceinline__ uint32_t ex2_fma_a(float s0, float s1) {
    const float M = 98304.f + 127.f - 460.f;
    uint32_t t0 = __float_as_uint(s0 + M), t1 = __float_as_uint(s1 + M), x;
    asm("prmt.b32 %0, %1, %2, 0x5410;" : "=r"(x) : "r"(t0), "r"(t1));
    return x;
}
__device__ __forceinline__ uint32_t ex2_fma_b(uint32_t x, uint32_t fmask) {
    uint32_t v, w, r;
    asm("lop3.b32 %0, %1, %2, 0x48004800, 0xEA;" : "=r"(v) : "r"(x), "r"(fmask));
    asm("fma.rn.f16x2 %0, %1, %2, %3;" : "=r"(w) : "r"(v), "r"(0x46944694u), "r"(0xD300D300u));
    asm("{.reg .b32 n; neg.f16x2 n, %1; fma.rn.f16x2 %0, n, %1, %2;}" : "=r"(r) : "r"(w), "r"(0xE5F5E5F5u));
    return x + r - 0x10000u;
}
__device__ __forceinline__ uint32_t exp_pair(float a, float b, int idx, uint32_t fmask) {
    if ((PAT >> idx) & 1) return ex2_fma_b(ex2_fma_a(a, b), fmask);
    return pack(ex2(a), ex2(b));
}
__device__ __forceinline__ void mma16816(float (&d)[4], const uint32_t (&a)[4], uint32_t b0, uint32_t b1) {
    asm volatile("mma.sync.aligned.m16n8k16.row.col.f32.bf16.bf16.f32 {%0,%1,%2,%3}, {%4,%5,%6,%7}, {%8,%9}, {%0,%1,%2,%3};"
        : "+f"(d[0]), "+f"(d[1]), "+f"(d[2]), "+f"(d[3]) : "r"(a[0]), "r"(a[1]), "r"(a[2]), "r"(a[3]), "r"(b0), "r"(b1));
}
__device__ __forceinline__ uint32_t movT(uint32_t a) { uint32_t d; asm volatile("movmatrix.sync.aligned.m8n8.trans.b16 %0, %1;" : "=r"(d) : "r"(a)); return d; }

__device__ __forceinline__ void attn_true_max(const uint32_t (&q)[4], float (&o)[12], int lane) {
    float m0 = -INFINITY, m1 = -INFINITY;
#pragma unroll 1
    for (int kg = 0; kg < 256; kg++) {
        const uint32_t* kb = &g_kv[kg >> 3][(kg & 7) * 64 + lane];
        float s[4] = {0.f, 0.f, 0.f, 0.f};
        mma16816(s, q, __ldcg(kb), __ldcg(kb + 32));
        m0 = fmaxf(m0, fmaxf(s[0], s[1])); m1 = fmaxf(m1, fmaxf(s[2], s[3]));
    }
    m0 = quad_max(m0); m1 = quad_max(m1);
    float a0[4] = {0.f, 0.f, 0.f, 0.f}, a1[4] = {0.f, 0.f, 0.f, 0.f}, a2[4] = {0.f, 0.f, 0.f, 0.f};
#pragma unroll 1
    for (int kg = 0; kg < 256; kg += 2) {
        const uint32_t* kb = &g_kv[kg >> 3][(kg & 7) * 64 + lane];
        const uint32_t* vb = &g_kv[kg >> 3][512 + (kg & 7) * 32 + lane];
        float s[4] = {0.f, 0.f, 0.f, 0.f}, t[4] = {0.f, 0.f, 0.f, 0.f};
        mma16816(s, q, __ldcg(kb), __ldcg(kb + 32));
        mma16816(t, q, __ldcg(kb + 64), __ldcg(kb + 96));
        uint32_t p[4] = {pack(ex2(s[0] - m0), ex2(s[1] - m0)), pack(ex2(s[2] - m1), ex2(s[3] - m1)),
                         pack(ex2(t[0] - m0), ex2(t[1] - m0)), pack(ex2(t[2] - m1), ex2(t[3] - m1))};
        mma16816(a0, p, movT(__ldcg(vb)), movT(__ldcg(vb + 32)));
        mma16816(a1, p, movT(__ldcg(vb + 256)), movT(__ldcg(vb + 288)));
        mma16816(a2, p, 0x3F803F80u, 0x3F803F80u);
    }
#pragma unroll
    for (int i = 0; i < 4; i++) { o[i] = a0[i]; o[4 + i] = a1[i]; o[8 + i] = a2[i]; }
}

#define G_STAGE(WG, ACC, U, PH, FIRST, DA, DASTEP, DB, DBSTEP)                                         \
    do {                                                                                               \
        mbar_wait(BAR(B_FULL + (U)), PH);                                                              \
        _Pragma("unroll") for (int ks_ = 0; ks_ < 4; ks_++) {                                          \
            if (ks_ % GB == 0) wfence();                                                               \
            WG(ACC, (DA) + (uint64_t)(ks_ * (DASTEP)), (DB) + (uint64_t)(ks_ * (DBSTEP)), ks_ > 0 || !(FIRST)); \
            if (ks_ % GB == GB - 1) { wcommit(); wwait<GD>(); }                                        \
            if (GD && ks_ == GD * GB - 1 && lane == 0 && !(FIRST)) mbar_arrive(BAR(B_EMPTY + (((U) + 3) & 3)));  \
        }                                                                                              \
        if (!GD && lane == 0) mbar_arrive(BAR(B_EMPTY + (U)));                                         \
    } while (0)
#define G_DRAIN(ACC, U) do { wwait<0>(); if (GD && lane == 0) mbar_arrive(BAR(B_EMPTY + (U))); pin(ACC); } while (0)
#define RING(U) (sb + SM_RING + (U) * STAGE)
#define SM_OL (SM_RING + 3 * STAGE)
#define WO_AT(U) ((U) < 2 ? RING(U) : sb + SM_X + ((U) - 2) * 32768)
#define Q_AT(W, T_) ((W) == 0 ? SM_Q + (T_) * 2048 : (T_) < 2 ? SM_Q + 8192 + (T_) * 2048 : SM_RING + (T_) * STAGE + 30720)

__global__ void __launch_bounds__(512, 1)
fused_kernel(const __grid_constant__ Maps maps, const __nv_bfloat16* __restrict__ wsp, const __nv_bfloat16* __restrict__ wout,
             const __nv_bfloat16* __restrict__ wo, const __nv_bfloat16* __restrict__ wk, const __nv_bfloat16* __restrict__ wv,
             const __nv_bfloat16* __restrict__ bsp, const __nv_bfloat16* __restrict__ gatew,
             __nv_bfloat16* __restrict__ out)
{
    extern __shared__ __align__(1024) uint8_t sp[];
    constexpr uint32_t sb = 1024;
    if ((uint32_t)__cvta_generic_to_shared(sp) != sb) return;
    const int tid = threadIdx.x, lane = tid & 31;
    const int warp = __shfl_sync(~0u, tid >> 5, 0), wg = warp >> 2, wq4 = warp & 3;
    const int T = blockIdx.x >> 2, j = blockIdx.x & 3;
    constexpr uint32_t bar = sb + SM_BAR;
#define BAR(i) (bar + 8u * (uint32_t)(i))

#define EPOCH() (*(volatile uint32_t*)(sp + SM_EPOCH))
#define CTA_SYNC() asm volatile("bar.sync 0, 512;" ::: "memory")

    uint4 ld[16], gwv;
    if (wg == 2) {
#pragma unroll
        for (int i = 0; i < 16; i++) ld[i] = ldg_stream((const uint4*)(i < 8 ? wk : wv) + (i & 7) * 128 + tid - 256);
        gwv = tid < 320 ? ldg_stream((const uint4*)gatew + tid - 256) : make_uint4(0, 0, 0, 0);
    } else if (wg == 3 && elect()) {
        if (wq4 == 0) {
#pragma unroll
            for (int k = 0; k < 12; k++) mbar_init(BAR(B_H + k), 1);
            fence_async_smem();
#pragma unroll
            for (int k = 0; k < 4; k++) {
                mbar_expect(BAR(B_X + k), 16384);
                tma3d(sb + SM_X + k * 16384, &maps.x, 0, T * 64, k * 2, BAR(B_X + k));
            }
#pragma unroll
            for (int k = 0; k < 8; k++) {
                mbar_expect(BAR(B_H + k), 16384);
                tma2d(RING(0) + k * 16384, &maps.wq, j * 128 + (k >> 2) * 64, (k & 3) * 128, BAR(B_H + k));
            }
        } else if (wq4 == 1) {
#pragma unroll
            for (int i = 0; i < 4; i++) {
                mbar_init(BAR(B_FULL + i), 1); mbar_init(BAR(B_EMPTY + i), 4);
                mbar_init(BAR(B_KVF + i), 1);  mbar_init(BAR(B_KVE + i), 8);
            }
            mbar_init(BAR(B_XDEAD), 4); mbar_init(BAR(B_KN), 1); mbar_init(BAR(B_PUB), 4); mbar_init(BAR(B_Q0), 1); mbar_init(BAR(B_KVM), 1); mbar_init(BAR(B_KVD), 1); mbar_init(BAR(B_OL), 8); mbar_init(BAR(B_OL + 1), 8); mbar_init(BAR(B_KV0), 1);
            *(volatile uint32_t*)(sp + SM_EPOCH + 8) = 0x007F007Fu;
            fence_async_smem();
        } else if (wq4 == 2) {
            *(volatile uint32_t*)(sp + SM_EPOCH) = (atomicAdd(&g_launch_ctr, 1u) >> 7) + 1u;
        } else {
#pragma unroll
            for (int i = 0; i < 6; i++) asm volatile("prefetch.tensormap [%0];" :: "l"(&maps.x + i) : "memory");
        }
    }
    __syncwarp();
    if (wg == 3) asm volatile("bar.arrive 0, 512;" ::: "memory");
    __syncwarp();

    if (wg == 3) {
        asm volatile("setmaxnreg.dec.sync.aligned.u32 24;");
        bar_sync(4);
        if (wq4 == 0) {
#define FILL(U, PH, BYTES, ...) do { mbar_wait(BAR(B_EMPTY + (U)), PH); [[maybe_unused]] constexpr uint32_t st = RING(U); constexpr uint32_t fb = BAR(B_FULL + (U)); \
                                     if (elect()) { mbar_expect(fb, BYTES); __VA_ARGS__ } } while (0)
#define FOR4(...) do { { constexpr int u = 0; __VA_ARGS__ } { constexpr int u = 1; __VA_ARGS__ } { constexpr int u = 2; __VA_ARGS__ } { constexpr int u = 3; __VA_ARGS__ } } while (0)
#pragma unroll 1
            for (int g = 0; g < 4; g++) {
                const int r = (g & 1) * 256, c0 = (g < 2 ? 688 : 0) + 176 * j;
                FOR4(FILL(u, g & 1, 24576, tma2d(st, &maps.win, c0, r + u * 64, fb); tma2d(st + 8192, &maps.win, c0 + 64, r + u * 64, fb);
                                           tma2d(st + 16384, &maps.win, c0 + 128, r + u * 64, fb);););
            }
            if (lane == 0) { PROF_P(37); }
            const uint32_t ep = EPOCH();
            poll_all(&g_z_flag[j][lane], ep);
            fence_async_global();
            if (lane == 0) { PROF_P(38); }
#pragma unroll 1
            for (int g = 0; g < 8; g++)
                FOR4(FILL(u, g & 1, 8192 + 22528, tma2d(st, &maps.wsp, g * 256 + u * 64, T * 64, fb); bulk_ld(st + 8192, g_z2n[j][g * 4 + u], 22528, fb);););
            if (lane == 0) { PROF_P(39); }
            poll_all(&g_u_flag[T], 4 * ep);
            fence_async_global();
            if (lane == 0) { PROF_P(40); }
#pragma unroll 1
            for (int g = 0; g < 3; g++)
                FOR4(if (u < 3 || g < 2) FILL(u, g & 1, 24576, bulk_ld(st, &g_u[T][(g * 4 + u) * 2048], 8192, fb);
                                              tma2d(st + 8192, &maps.wout, j * 128, g * 256 + u * 64, fb); tma2d(st + 16384, &maps.wout, j * 128 + 64, g * 256 + u * 64, fb);););
            FOR4(FILL((u + 3) & 3, u > 0, 32768, tma2d(WO_AT((u + 3) & 3), &maps.wo, j * 128, ((j + u) & 3) * 128, fb);
                                                 tma2d(WO_AT((u + 3) & 3) + 16384, &maps.wo, j * 128 + 64, ((j + u) & 3) * 128, fb);););
            PROF_END();
        } else if (wq4 == 1) {
            const uint32_t ep = EPOCH();
            poll_all(&g_kv_flag[lane], ep);
            fence_async_global();
#pragma unroll 1
            for (int i = 2; i < 16; i++) {
                const uint32_t fb = BAR(B_KVF + (i & 1)), dst = sb + SM_KV + (i & 1) * 2 * KVSLOT;
                mbar_wait(BAR(B_KVE + (i & 1)), ((i >> 1) & 1) ^ 1);
                if (elect()) {
                    mbar_expect(fb, 8192);
                    bulk_ld(dst, g_kv[(T + 2 * i) & 31], 4096, fb);
                    bulk_ld(dst + KVSLOT, g_kv[(T + 2 * i + 1) & 31], 4096, fb);
                }
            }
        } else if (wq4 == 2) {
            if (lane == 0) {
                uint32_t ph = 0;
                if (j == 0) { mbar_wait(BAR(B_PUB), ph); ph ^= 1; red_rel(&g_kv_flag[T]); PROF_P(24); }
                mbar_wait(BAR(B_PUB), ph); ph ^= 1; PROF_P(30); red_rel(&g_st_flag[T]); PROF_P(31);
                mbar_wait(BAR(B_PUB), ph); ph ^= 1; PROF_P(32); red_rel(&g_z_flag[j][T]); PROF_P(33);
                mbar_wait(BAR(B_PUB), ph); PROF_P(34); red_rel(&g_u_flag[T]); PROF_P(35);
            }
            __syncwarp();
            PROF_END();
        } else {
            poll_all(&g_kv_flag[lane], EPOCH());
            float4 km = __ldcg((const float4*)g_kmax[lane]);
            float kn = fmaxf(fmaxf(km.x, km.y), fmaxf(km.z, km.w));
#pragma unroll
            for (int of = 16; of; of >>= 1) kn = fmaxf(kn, __shfl_xor_sync(~0u, kn, of));
            if (lane == 0) { *(volatile float*)(sp + SM_EPOCH + 4) = kn; mbar_arrive(BAR(B_KN)); }
            if (lane < 16) l2_prefetch(wsp + (size_t)(T * 64 + j * 16 + lane) * 2048, 4096);
            else if (lane < 20) l2_prefetch(wo + (size_t)(blockIdx.x * 4 + lane - 16) * 512, 1024);
            else if (lane < 26 && blockIdx.x * 6 + lane - 20 < 688) l2_prefetch(wout + (size_t)(blockIdx.x * 6 + lane - 20) * 512, 1024);
        }
    } else if (wg == 2) {
        const int r0 = wq4 * 16 + (lane >> 2);
        const uint64_t dx = mkdesc(sb + SM_X, 16, 1024, 1);
        PROF_T(0);
        {
            const int t = tid - 256;
#pragma unroll
            for (int i = 0; i < 16; i++) *(uint4*)(sp + SM_KV + ((i >> 3) * 2 + (t & 1)) * 8192 + ((i & 7) * 64 + (t >> 1)) * 16) = ld[i];
            if (t < 80) *(uint4*)(sp + SM_GW + t * 16) = gwv;
            fence_async_smem();
            CTA_SYNC();
            float kv[16];
            const uint64_t db = mkdesc(sb + SM_KV, 128, 8192, 0);
#pragma unroll
            for (int h = 0; h < 4; h++) {
                mbar_wait(BAR(B_X + h), 0);
                if (h == 0) { PROF_T(13); } else if (h == 3) { PROF_T(14); }
                wfence();
#pragma unroll
                for (int ks = h * 8; ks < h * 8 + 8; ks++) wg_ss32(kv, dx + (uint64_t)((ks >> 2) * 512 + (ks & 3) * 2), db + (uint64_t)(ks * 16), ks > 0);
                wcommit();
            }
            if (QPRI && tid == 256) mbar_arrive(BAR(B_KVM));
            wwait<0>(); pin(kv);
            PROF_T(15);
            const uint32_t k0 = pack(kv[0], kv[1]), k1 = pack(kv[2], kv[3]), k2 = pack(kv[4], kv[5]), k3 = pack(kv[6], kv[7]);
            const uint32_t v0 = pack(kv[8], kv[9]), v1 = pack(kv[10], kv[11]), v2 = pack(kv[12], kv[13]), v3 = pack(kv[14], kv[15]);
            const uint32_t par = EPOCH() & 1;
            if (j == 0) {
                st_mail(&g_kvm[par][T][0][t], k0, k2, k1, k3);
                st_mail(&g_kvm[par][T][1][t], v0, v1, v2, v3);
            }
            bar_sync(3);
            uint32_t* ks = (uint32_t*)(sp + SM_KV) + wq4 * 128 + lane;
            uint32_t* vs = (uint32_t*)(sp + SM_KV) + 512 + wq4 * 64 + lane;
            ks[0] = k0; ks[32] = k2; ks[64] = k1; ks[96] = k3;
            vs[0] = v0; vs[32] = v1; vs[256] = v2; vs[288] = v3;
#pragma unroll
            for (int i = 0; i < 2; i++) {
                const int t2 = t + i * 128;
                *(uint4*)(sp + SM_KV + (t2 >> 6) * KVSLOT + 4096 + (t2 & 63) * 16) = make_uint4(0x3F803F80u, 0x3F803F80u, 0x3F803F80u, 0x3F803F80u);
            }
            if (tid == 256) mbar_arrive(BAR(B_KVD));
            fence_async_smem();
            bar_sync(3);
            if (tid == 256) mbar_arrive(BAR(B_KV0));
            if (j == 0) {
                uint32_t* kb = &g_kv[T][wq4 * 128 + lane];
                uint32_t* vb = &g_kv[T][512 + wq4 * 64 + lane];
                kb[0] = k0; kb[32] = k2; kb[64] = k1; kb[96] = k3;
                vb[0] = v0; vb[32] = v1; vb[256] = v2; vb[288] = v3;
                float n0 = bf_lo(k0) * bf_lo(k0) + bf_hi(k0) * bf_hi(k0) + bf_lo(k2) * bf_lo(k2) + bf_hi(k2) * bf_hi(k2);
                float n1 = bf_lo(k1) * bf_lo(k1) + bf_hi(k1) * bf_hi(k1) + bf_lo(k3) * bf_lo(k3) + bf_hi(k3) * bf_hi(k3);
                n0 = quad_sum(n0); n1 = quad_sum(n1);
                float vm = 0.f;
#pragma unroll
                for (int i = 8; i < 16; i++) vm = fmaf(kv[i], kv[i], vm);
                float nm = (n0 + n1 < 1e30f && vm < 1e9f) ? fmaxf(n0, n1) : INFINITY;
#pragma unroll
                for (int o = 1; o < 32; o <<= 1) nm = fmaxf(nm, __shfl_xor_sync(~0u, nm, o));
                if (lane == 0) g_kmax[T][wq4] = nm;
                warp_arrive(BAR(B_PUB), lane);
                st_relaxed4(&g_kvm[par ^ 1][T][0][t], 0, 0, 0, 0);
                st_relaxed4(&g_kvm[par ^ 1][T][1][t], 0, 0, 0, 0);
            }
            uint4 m[6];
#pragma unroll
            for (int i = 0; i < 6; i++) m[i] = ld_relaxed4(&g_kvm[par][(T + 1 + (i >> 1)) & 31][i & 1][t]);
#pragma unroll
            for (int pr = 0; pr < 2; pr++) {
#pragma unroll 1
                for (int spins = 0; spins < 0x400000; spins++) {
                    uint32_t lo = ~0u;
#pragma unroll
                    for (int i = 2 * pr; i < 2 + 4 * pr; i++) lo = min(lo, min4(m[i]));
                    if (__all_sync(~0u, lo != 0)) break;
#pragma unroll
                    for (int i = 2 * pr; i < 6; i++) if (min4(m[i]) == 0) m[i] = ld_relaxed4(&g_kvm[par][(T + 1 + (i >> 1)) & 31][i & 1][t]);
                }
#pragma unroll
                for (int i = pr; i < 1 + 2 * pr; i++) {
                    uint32_t* kd = ks + (i + 1) * (KVSLOT / 4);
                    uint32_t* vd = vs + (i + 1) * (KVSLOT / 4);
                    kd[0] = m[2 * i].x; kd[32] = m[2 * i].y; kd[64] = m[2 * i].z; kd[96] = m[2 * i].w;
                    vd[0] = m[2 * i + 1].x; vd[32] = m[2 * i + 1].y; vd[256] = m[2 * i + 1].z; vd[288] = m[2 * i + 1].w;
                }
                fence_async_smem();
                bar_sync(3);
                if (tid == 256) mbar_arrive(BAR(B_KVF + pr));
            }
        }
        asm volatile("setmaxnreg.inc.sync.aligned.u32 136;");
        PROF_T(1);
        float acc[88];
#define ZS(i) ((uint4*)(sp + SM_RING + ((i) >> 2) * STAGE + 24576 + ((i) & 3) * 2048))[tid - 256]
        uint4* z1s = (uint4*)(sp + SM_X) + tid - 256;
#pragma unroll 1
        for (int g = 0; g < 2; g++)
#pragma unroll
            for (int u = 0; u < 4; u++) G_STAGE(wg_ss176, acc, u, g, g == 0 && u == 0, dx + (uint64_t)(g * 2048 + u * 512), 2, mkdesc(RING(u), 8192, 1024, 1), 128);
        G_DRAIN(acc, 3);
        PROF_T(2);
        {
            float s0 = 0.f, s1 = 0.f;
#pragma unroll
            for (int i = 0; i < 22; i++) {
#pragma unroll
                for (int e = 0; e < 4; e++) acc[4 * i + e] = gelu2(acc[4 * i + e]);
                s0 += acc[4 * i] + acc[4 * i + 1]; s1 += acc[4 * i + 2] + acc[4 * i + 3];
                if (i & 1) ZS(i >> 1) = make_uint4(pack(acc[4 * i - 4], acc[4 * i - 3]), pack(acc[4 * i - 2], acc[4 * i - 1]),
                                                           pack(acc[4 * i], acc[4 * i + 1]), pack(acc[4 * i + 2], acc[4 * i + 3]));
            }
            const float inv = j == 3 ? 1.f / 160.f : 1.f / 176.f;
            const float m0 = quad_sum(s0) * inv, m1 = quad_sum(s1) * inv;
            float v0 = 0.f, v1 = 0.f;
#pragma unroll
            for (int i = 0; i < 22; i++) {
                const float a = acc[4 * i] - m0, b = acc[4 * i + 1] - m0, c = acc[4 * i + 2] - m1, d = acc[4 * i + 3] - m1;
                v0 = fmaf(a, a, fmaf(b, b, v0)); v1 = fmaf(c, c, fmaf(d, d, v1));
            }
            const float pad = j == 3 ? 16.f : 0.f;
            v0 = fmaf(-pad * m0, m0, quad_sum(v0)); v1 = fmaf(-pad * m1, m1, quad_sum(v1));
#pragma unroll
            for (int i = 0; i < 8; i++) st_relaxed4(&g_o[T][j][i >> 1][(i & 1) * 128 + tid - 256], 0, 0, 0, 0);
            if ((lane & 3) == 0) { g_stats[T][j][r0] = make_float2(m0, v0); g_stats[T][j][r0 + 8] = make_float2(m1, v1); }
            warp_arrive(BAR(B_PUB), lane);
        }
        PROF_T(3);
#pragma unroll 1
        for (int g = 0; g < 2; g++)
#pragma unroll
            for (int u = 0; u < 4; u++) G_STAGE(wg_ss176, acc, u, g, g == 0 && u == 0, dx + (uint64_t)(g * 2048 + u * 512), 2, mkdesc(RING(u), 8192, 1024, 1), 128);
        G_DRAIN(acc, 3);
        PROF_T(4);
        {
            poll_all(&g_st_flag[T], 4 * EPOCH());
            PROF_T(36);
            uint32_t sc[2], sh[2];
#pragma unroll
            for (int h = 0; h < 2; h++) {
                float2 s[4];
#pragma unroll
                for (int i = 0; i < 4; i++) s[i] = __ldcg(&g_stats[T][i][r0 + 8 * h]);
                const float m = (176.f * (s[0].x + s[1].x + s[2].x) + 160.f * s[3].x) * (1.f / 688.f);
                float v = s[0].y + s[1].y + s[2].y + s[3].y;
#pragma unroll
                for (int i = 0; i < 4; i++) v = fmaf((i == 3 ? 160.f : 176.f) * (s[i].x - m), s[i].x - m, v);
                const float r = bf_lo(pack(rsqrtf(fmaxf(v, 0.f) * (1.f / 688.f) + 4e-5f), 0.f));
                sc[h] = pack(r, r); sh[h] = pack(-m * r, -m * r);
            }
            uint32_t* zb = &g_z2n[j][T][wq4 * 64 + lane];
#pragma unroll
            for (int i = 0; i < 11; i++) {
                const uint4 z = ZS(i);
                zb[i * 512] = bf2_fma(z.x, sc[0], sh[0]); zb[i * 512 + 32] = bf2_fma(z.y, sc[1], sh[1]);
                zb[i * 512 + 256] = bf2_fma(z.z, sc[0], sh[0]); zb[i * 512 + 288] = bf2_fma(z.w, sc[1], sh[1]);
            }
            warp_arrive(BAR(B_PUB), lane);
        }
        PROF_T(5);
        {
            float gl[4];
            const uint64_t dg = mkdesc(sb + SM_GW, 16, 128, 0);
            wfence();
#pragma unroll
            for (int ks2 = 0; ks2 < 32; ks2++) wg_ss8k(gl, dx + (uint64_t)((ks2 >> 2) * 512 + (ks2 & 3) * 2), dg + (uint64_t)(ks2 * 2), ks2 > 0);
            wcommit();
            wwait<0>(); pin(gl);
            if ((lane & 3) == 0) {
                ((float*)(sp + SM_GATE))[r0] = __fdividef(1.f, 1.f + __expf(-gl[0]));
                ((float*)(sp + SM_GATE))[r0 + 8] = __fdividef(1.f, 1.f + __expf(-gl[2]));
            }
            bar_sync(3);
        }
#pragma unroll
        for (int i = 0; i < 11; i++)
            z1s[i * 128] = make_uint4(pack(gelu2(acc[8 * i]), gelu2(acc[8 * i + 1])), pack(gelu2(acc[8 * i + 2]), gelu2(acc[8 * i + 3])),
                                      pack(gelu2(acc[8 * i + 4]), gelu2(acc[8 * i + 5])), pack(gelu2(acc[8 * i + 6]), gelu2(acc[8 * i + 7])));
        PROF_T(6);
#pragma unroll 1
        for (int g = 0; g < 8; g++)
#pragma unroll
            for (int u = 0; u < 4; u++) G_STAGE(wg_ss176, acc, u, g & 1, g == 0 && u == 0, mkdesc(RING(u), 16, 1024, 1), 2, mkdesc(RING(u) + 8192, 128, 1024, 0), 16);
        G_DRAIN(acc, 3);
        PROF_T(7);
        {
            const float* gs = (const float*)(sp + SM_GATE);
            const float g0 = 0.5f - 0.5f * gs[r0], g1 = 0.5f - 0.5f * gs[r0 + 8];
            const float b0 = __bfloat162float(bsp[T * 64 + r0]) * g0, b1 = __bfloat162float(bsp[T * 64 + r0 + 8]) * g1;
            uint32_t* ub = &g_u[T][j * 22 * 256 + wq4 * 64 + lane];
#pragma unroll
            for (int i = 0; i < 11; i++) {
                const uint4 z = z1s[i * 128];
                const float* a = acc + 8 * i;
                const bool live = i < 10 || j != 3;
                const uint32_t u0 = bf2_mul(z.x, pack(fmaf(a[0], g0, b0), fmaf(a[1], g0, b0))), u1 = bf2_mul(z.y, pack(fmaf(a[2], g1, b1), fmaf(a[3], g1, b1)));
                const uint32_t u2 = bf2_mul(z.z, pack(fmaf(a[4], g0, b0), fmaf(a[5], g0, b0))), u3 = bf2_mul(z.w, pack(fmaf(a[6], g1, b1), fmaf(a[7], g1, b1)));
                ub[i * 512] = live ? u0 : 0u; ub[i * 512 + 32] = live ? u1 : 0u; ub[i * 512 + 256] = live ? u2 : 0u; ub[i * 512 + 288] = live ? u3 : 0u;
            }
            warp_arrive(BAR(B_PUB), lane);
        }
        PROF_T(8);
        float oacc[64];
#pragma unroll 1
        for (int g = 0; g < 3; g++)
#pragma unroll
            for (int u = 0; u < 4; u++)
                if (u < 3 || g < 2) G_STAGE(wg_ss128, oacc, u, g & 1, g == 0 && u == 0, mkdesc(RING(u), 1024, 128, 0), 128, mkdesc(RING(u) + 8192, 8192, 1024, 1), 128);
        G_DRAIN(oacc, 2);
        if (lane == 0) mbar_arrive(BAR(B_XDEAD));
        PROF_T(9);
#pragma unroll
        for (int i = 0; i < 4; i++) mbar_wait(BAR(B_FULL + ((i + 3) & 3)), i > 0);
#define OFRAG(e, b, i) &g_o[T][(j + (b)) & 3][2 * (e) + ((i) & 1)][((i) >> 1) * 128 + tid - 256]
#define OLOAD(e, b, F) _Pragma("unroll") for (int i = 0; i < 4; i++) F[i] = ld_relaxed4(OFRAG(e, b, i))
#define OLOCAL(e, F) _Pragma("unroll") for (int i = 0; i < 4; i++) F[i] = ((const uint4*)(sp + SM_OL))[((e) * 4 + i) * 128 + tid - 256]
#define OREADY(F) __all_sync(~0u, min(min(min4(F[0]), min4(F[1])), min(min4(F[2]), min4(F[3]))) != 0)
#define ORETRY(e, b, F) _Pragma("unroll") for (int i = 0; i < 4; i++) if (min4(F[i]) == 0) F[i] = ld_relaxed4(OFRAG(e, b, i))
#define OMMA(e, b, F) do { wfence(); _Pragma("unroll") for (int i = 0; i < 4; i++)                                     \
                            wg_rs128(oacc, F[i].x, F[i].y, F[i].z, F[i].w, mkdesc(WO_AT(((b) + 3) & 3), 16384, 1024, 1) \
                                     + (uint64_t)(((i >> 1) * 4 + (i & 1)) * 128 + (e) * 256)); wcommit(); } while (0)
#define SPIN(COND) _Pragma("unroll 1") for (int spins = 0; spins < 0x400000 && !(COND); spins++)
        {
            uint4 f0[4], f1[4];
            mbar_wait(BAR(B_OL), 0);
            OLOCAL(0, f0); OLOAD(0, 1, f1);
            OMMA(0, 0, f0); wwait<0>();
            OLOAD(0, 2, f0);
            SPIN(OREADY(f1)) { ORETRY(0, 1, f1); }
            OMMA(0, 1, f1); wwait<0>();
            OLOAD(0, 3, f1);
            SPIN(OREADY(f0)) { ORETRY(0, 2, f0); }
            OMMA(0, 2, f0);
            SPIN(OREADY(f1)) { ORETRY(0, 3, f1); }
            OMMA(0, 3, f1); wwait<0>();
        }
        PROF_T(27);
        asm volatile("setmaxnreg.inc.sync.aligned.u32 168;");
        {
            uint4 f0[4], f1[4], f2[4], f3[4];
            OLOAD(1, 1, f1); OLOAD(1, 2, f2); OLOAD(1, 3, f3);
            mbar_wait(BAR(B_OL + 1), 0);
            OLOCAL(1, f0);
            OMMA(1, 0, f0);
            SPIN(OREADY(f1)) { ORETRY(1, 1, f1); ORETRY(1, 2, f2); ORETRY(1, 3, f3); }
            OMMA(1, 1, f1);
            SPIN(OREADY(f2)) { ORETRY(1, 2, f2); ORETRY(1, 3, f3); }
            OMMA(1, 2, f2);
            SPIN(OREADY(f3)) { ORETRY(1, 3, f3); }
            PROF_T(28);
            OMMA(1, 3, f3);
            wwait<0>();
        }
        pin(oacc);
        PROF_T(10);
        const int c4 = lane & 3;
        uint4* ob = (uint4*)(out + (size_t)(T * 64 + r0) * 512 + j * 128) + c4;
#pragma unroll
        for (int g = 0; g < 8; g++) {
            const int i0 = (g >> 1) * 16 + (g & 1) * 2;
            uint32_t w0 = pack(oacc[i0], oacc[i0 + 1]), w1 = pack(oacc[i0 + 4], oacc[i0 + 5]);
            uint32_t w2 = pack(oacc[i0 + 8], oacc[i0 + 9]), w3 = pack(oacc[i0 + 12], oacc[i0 + 13]);
            uint32_t a = __shfl_xor_sync(~0u, (c4 & 1) ? w0 : w1, 1), b = __shfl_xor_sync(~0u, (c4 & 1) ? w2 : w3, 1);
            if (c4 & 1) { w0 = a; w2 = b; } else { w1 = a; w3 = b; }
            a = __shfl_xor_sync(~0u, (c4 & 2) ? w0 : w2, 2); b = __shfl_xor_sync(~0u, (c4 & 2) ? w1 : w3, 2);
            if (c4 & 2) { w0 = a; w1 = b; } else { w2 = a; w3 = b; }
            ob[(g & 1) * 8 * 64 + (g >> 1) * 4] = make_uint4(w0, w1, w2, w3);
        }
        PROF_T(11);
        PROF_END();
    } else {
        CTA_SYNC();
        float qn;
#define QS(T_) ((uint32_t*)(sp + Q_AT(wg, T_)) + wq4 * 64 + lane)
        {
            float qa[32];
            const uint64_t dx = mkdesc(sb + SM_X, 16, 1024, 1);
            const uint64_t db = mkdesc(RING(0), 8192, 1024, 1) + (uint64_t)(wg * (2 * STAGE / 16));
#pragma unroll
            for (int h = 0; h < 4; h++) {
                mbar_wait(BAR(B_X + h), 0);
                mbar_wait(BAR(B_H + h) + wg * 32, 0);
                if (QPRI && h == 0) mbar_wait(wg ? BAR(B_Q0) : BAR(B_KVM), 0);
                wfence();
#pragma unroll
                for (int ks = h * 8; ks < h * 8 + 8; ks++) wg_ss64(qa, dx + (uint64_t)((ks >> 2) * 512 + (ks & 3) * 2), db + (uint64_t)(ks * 128), ks > 0);
                wcommit();
            }
            if (QPRI && tid == 0) mbar_arrive(BAR(B_Q0));
            wwait<0>();
            if (lane == 0) { mbar_arrive(BAR(B_EMPTY + 2 * wg)); mbar_arrive(BAR(B_EMPTY + 2 * wg + 1)); }
            pin(qa);
            const float c = 0.25f * 1.4426950408889634f;
            float n[8];
            mbar_wait(BAR(B_KVD), 0);
            if (wg) bar_sync(2);
#pragma unroll
            for (int t = 0; t < 4; t++) {
#pragma unroll
                for (int i = 0; i < 4; i++) QS(t)[(i >> 1) * 256 + (i & 1) * 32] = pack(qa[8 * t + 2 * i] * c, qa[8 * t + 2 * i + 1] * c);
#pragma unroll
                for (int h = 0; h < 2; h++) {
                    const float* a = qa + 8 * t + 2 * h;
                    n[2 * t + h] = fmaf(a[0], a[0], fmaf(a[1], a[1], fmaf(a[4], a[4], a[5] * a[5])));
                }
            }
            fence_async_smem();
            bar_sync(1 + wg);
#pragma unroll
            for (int i = 0; i < 4; i++) n[i] = ((lane & 1) ? n[4 + i] : n[i]) + __shfl_xor_sync(~0u, (lane & 1) ? n[i] : n[4 + i], 1);
#pragma unroll
            for (int i = 0; i < 2; i++) n[i] = ((lane & 2) ? n[2 + i] : n[i]) + __shfl_xor_sync(~0u, (lane & 2) ? n[i] : n[2 + i], 2);
            qn = (n[0] + n[1] < 1e30f ? fmaxf(n[0], n[1]) : INFINITY) * (c * c * 1.01f);
        }
        asm volatile("setmaxnreg.inc.sync.aligned.u32 176;");
        PROF_T(16 + wg * 4);
        float o[4][12], s[2][32];
        uint32_t p[2][16];
#pragma unroll
        for (int t = 0; t < 4; t++) zero(o[t]);
#pragma unroll
        for (int i = 0; i < 32; i++) { s[0][i] = 0.f; s[1][i] = -127.f; }
        pin(s[0]); pin(s[1]);
#pragma unroll
        for (int i = 0; i < 16; i++) p[0][i] = 0;
        pinu(p[0]);
        const uint32_t fmask = *(volatile uint32_t*)(sp + SM_EPOCH + 8);
        const uint64_t dk0 = mkdesc(sb + SM_KV, 128, 256, 0), dv0 = mkdesc(sb + SM_KV + 2048, 128, 1024, 0);
        constexpr uint32_t SL = KVSLOT / 16;
        uint32_t kvok = W2, oc = 0, op = 0u - KVSLOT / 16;
        bool early = false;
        float g0, g1;
#define HEAD(it) (((it) & 1) + (((it) >> 2) & 1) * 2)
#define HALF(it) (((it) >> 1) & 1)
#define PV(T_, B_, DV_) _Pragma("unroll") for (int k = 0; k < 4; k++) wg_pv24(o[T_], p[B_][4 * k], p[B_][4 * k + 1], p[B_][4 * k + 2], p[B_][4 * k + 3], (DV_) + k * 16)
#define EXPS(S_) _Pragma("unroll") for (int i = 0; i < 16; i++) p[S_][i] = exp_pair(s[S_][2 * i], s[S_][2 * i + 1], i, fmask)
#define SAFE(T_) __all_sync(~0u, qn <= 10000.f && fminf(fminf(o[T_][8], o[T_][10]), fminf(o[T_ + 1][8], o[T_ + 1][10])) >= 9.3e-10f)
#define SEND(T_) do { const float f0 = __fdividef(g0, o[T_][8]), f1 = __fdividef(g1, o[T_][10]);                                     \
                      const uint4 w = make_uint4(pack(o[T_][0] * f0, o[T_][1] * f0), pack(o[T_][2] * f1, o[T_][3] * f1),            \
                                                 pack(o[T_][4] * f0, o[T_][5] * f0), pack(o[T_][6] * f1, o[T_][7] * f1));           \
                      st_mail(&g_o[T][j][T_][tid], w.x, w.y, w.z, w.w);                                                              \
                      ((uint4*)(sp + SM_OL))[(((T_) >> 1) * 4 + wg * 2 + ((T_) & 1)) * 128 + (tid & 127)] = w; } while (0)
        mbar_wait(BAR(B_KV0), 0);
#pragma unroll 1
        for (int i2 = 0; i2 < 16; i2++) {
            if (__builtin_expect(!kvok, 0)) mbar_wait(BAR(B_KVF + (i2 & 1)), (i2 >> 1) & 1);
            if (i2 == 0) { PROF_T(17 + wg * 4); }
#pragma unroll
            for (int it = 0; it < 8; it++) {
                const int cur = (it & 1) ^ 1, nxt = it & 1, ip = (it + 6) & 7;
                if (W2 && it == 2 && __builtin_expect(i2 == 0, 0)) mbar_wait(BAR(B_KVF), 0);
                wfence();
                wg_qk64s(s[nxt], mkdesc(sb + Q_AT(wg, HEAD(it)), 1024, 128, 0), dk0 + (uint64_t)(oc + HALF(it) * SL));
                wcommit();
                PV(HEAD(ip), nxt, dv0 + (uint64_t)((it < 2 ? op : oc) + HALF(ip) * SL));
                wcommit();
                if (it > 0) wwait<2>();
                if (it == 2 && lane == 0 && i2 > 0) mbar_arrive(BAR(B_KVE + ((i2 & 1) ^ 1)));
                if (it == 6 && __builtin_expect(i2 == 15, 0)) {
                    pin(o[0]); pin(o[1]);
                    mbar_wait(BAR(B_KN), 0);
                    mbar_wait(BAR(B_XDEAD), 0);
                    const volatile float* gs = (const volatile float*)(sp + SM_GATE) + wq4 * 16 + (lane >> 2);
                    g0 = gs[0]; g1 = gs[8];
                    qn *= *(volatile float*)(sp + SM_EPOCH + 4);
                    early = SAFE(0);
                    if (early) { SEND(0); SEND(1); warp_arrive(BAR(B_OL), lane); }
                }
                if (it == 7) kvok = mbar_test(BAR(B_KVF + ((i2 & 1) ^ 1)), ((i2 + 1) >> 1) & 1);
                pin(s[cur]);
                EXPS(cur);
                pinu(p[cur]);
            }
            wwait<0>();
            op = oc; oc ^= 2 * SL;
        }
        wfence();
        PV(2, 0, dv0 + (uint64_t)(3 * SL));
        wcommit();
        pin(s[1]);
        EXPS(1);
        wfence();
        PV(3, 1, dv0 + (uint64_t)(3 * SL));
        wcommit();
        wwait<0>();
#pragma unroll
        for (int t = 0; t < 4; t++) pin(o[t]);
        PROF_T(18 + wg * 4);
        if (__builtin_expect(!(early && SAFE(2)), 0)) {
#pragma unroll
            for (int t = 0; t < 4; t++) {
                const uint32_t q[4] = {QS(t)[0], QS(t)[32], QS(t)[256], QS(t)[288]};
                if (t >= 2 || !early) attn_true_max(q, o[t], lane);
                if (t < 2 && !early) SEND(t);
            }
            if (!early) warp_arrive(BAR(B_OL), lane);
        }
        SEND(2); SEND(3);
        warp_arrive(BAR(B_OL + 1), lane);
        asm volatile("setmaxnreg.dec.sync.aligned.u32 64;");
        PROF_T(19 + wg * 4);
        PROF_END();
    }
}

typedef CUresult (*EncodeFn)(CUtensorMap*, CUtensorMapDataType, cuuint32_t, void*, const cuuint64_t*, const cuuint64_t*, const cuuint32_t*,
                             const cuuint32_t*, CUtensorMapInterleave, CUtensorMapSwizzle, CUtensorMapL2promotion, CUtensorMapFloatOOBfill);

void make_map_x(EncodeFn enc, CUtensorMap* m, const void* p) {
    cuuint64_t dims[3] = {64, 2048, 8}, strides[2] = {1024, 128};
    cuuint32_t box[3] = {64, 64, 2}, es[3] = {1, 1, 1};
    enc(m, CU_TENSOR_MAP_DATA_TYPE_BFLOAT16, 3, const_cast<void*>(p), dims, strides, box, es, CU_TENSOR_MAP_INTERLEAVE_NONE,
        CU_TENSOR_MAP_SWIZZLE_128B, CU_TENSOR_MAP_L2_PROMOTION_L2_256B, CU_TENSOR_MAP_FLOAT_OOB_FILL_NONE);
}
void make_map(EncodeFn enc, CUtensorMap* m, const void* p, uint64_t rows, uint64_t cols, uint32_t brows, uint32_t bcols, CUtensorMapSwizzle sw) {
    cuuint64_t dims[2] = {cols, rows}, strides[1] = {cols * 2};
    cuuint32_t box[2] = {bcols, brows}, es[2] = {1, 1};
    enc(m, CU_TENSOR_MAP_DATA_TYPE_BFLOAT16, 2, const_cast<void*>(p), dims, strides, box, es, CU_TENSOR_MAP_INTERLEAVE_NONE, sw,
        CU_TENSOR_MAP_L2_PROMOTION_L2_256B, CU_TENSOR_MAP_FLOAT_OOB_FILL_NONE);
}

}

extern "C" void kernel_launch(void* const* d_in, const int* in_sizes, int n_in, void* d_out, int out_size) {
    void* fn = nullptr;
    cudaDriverEntryPointQueryResult qr;
    cudaGetDriverEntryPoint("cuTensorMapEncodeTiled", &fn, cudaEnableDefault, &qr);
    EncodeFn enc = (EncodeFn)fn;
    Maps m;
    make_map_x(enc, &m.x, d_in[0]);
    make_map(enc, &m.wq, d_in[1], 512, 512, 128, 64, CU_TENSOR_MAP_SWIZZLE_128B);
    make_map(enc, &m.wo, d_in[4], 512, 512, 128, 64, CU_TENSOR_MAP_SWIZZLE_128B);
    make_map(enc, &m.win, d_in[6], 512, 1376, 64, 64, CU_TENSOR_MAP_SWIZZLE_128B);
    make_map(enc, &m.wsp, d_in[7], 2048, 2048, 64, 64, CU_TENSOR_MAP_SWIZZLE_128B);
    make_map(enc, &m.wout, d_in[9], 688, 512, 64, 64, CU_TENSOR_MAP_SWIZZLE_128B);
    cudaFuncSetAttribute(fused_kernel, cudaFuncAttributeMaxDynamicSharedMemorySize, SM_TOTAL);
    fused_kernel<<<NCTA, 512, SM_TOTAL>>>(m, (const __nv_bfloat16*)d_in[7], (const __nv_bfloat16*)d_in[9], (const __nv_bfloat16*)d_in[4],
                                          (const __nv_bfloat16*)d_in[2], (const __nv_bfloat16*)d_in[3], (const __nv_bfloat16*)d_in[8], (const __nv_bfloat16*)d_in[10], (__nv_bfloat16*)d_out);
}
```
